```python
import torch

def _softmax(x, axis=-1):
    return torch.softmax(x, dim=axis)
def _gelu(x):
    return torch.nn.functional.gelu(x, approximate="tanh")
def _silu(x):
    return torch.nn.functional.silu(x)
def _sigmoid(x):
    return torch.sigmoid(x)
def _layernorm(x, axis=-1, eps=1e-5):
    m = x.mean(dim=axis, keepdim=True)
    v = x.var(dim=axis, keepdim=True, unbiased=False)
    return (x - m) / torch.sqrt(v + eps)
def _scatter_add(tgt, idx, src, axis=0):
    return tgt.clone().index_add_(axis, idx, src)
def _segment_sum(src, seg, n):
    out = torch.zeros((n,) + src.shape[1:], dtype=src.dtype)
    return out.index_add_(0, seg, src)
def _pad(x, pw):
    flat = tuple(v for pair in reversed(pw) for v in pair)
    return torch.nn.functional.pad(x, flat)

kernel_name = 'concat_heads__mha_block_cached__mha_block_cached__near_ridge'

def setup_inputs():

    _w = (lambda a: (lambda t: t.to(torch.bfloat16) if t.is_floating_point() else t)(torch.as_tensor(a)))
    def _A_setup():
        B, Sq, D = 8, 96, 448
        H, Sk, Dh = 16, 512, 256
        return {
            "x": _w((lambda *s: torch.randn(*s, dtype=torch.bfloat16) * 0.8)(B, Sq, D)),
            "k_cache": _w((lambda *s: torch.randn(*s, dtype=torch.bfloat16) * 0.8)(B, H, Sk, Dh)),
            "v_cache": _w((lambda *s: torch.randn(*s, dtype=torch.bfloat16) * 0.05)(B, H, Sk, Dh)),
            "wq": _w((lambda *s: torch.randn(*s, dtype=torch.bfloat16) * 0.8)(D, H * Dh) * (D ** -0.5)),
            "wo": _w((lambda *s: torch.randn(*s, dtype=torch.bfloat16) * 0.05)(H * Dh, D) * ((H * Dh) ** -0.5)),
        }
    _A_in = _A_setup()

    def _B_setup():
        B, Sq, D = 8, 96, 448
        H, Sk, Dh = 16, 512, 256
        return {
            "x": _w((lambda *s: torch.randn(*s, dtype=torch.bfloat16) * 0.8)(B, Sq, D)),
            "k_cache": _w((lambda *s: torch.randn(*s, dtype=torch.bfloat16) * 0.8)(B, H, Sk, Dh)),
            "v_cache": _w((lambda *s: torch.randn(*s, dtype=torch.bfloat16) * 0.05)(B, H, Sk, Dh)),
            "wq": _w((lambda *s: torch.randn(*s, dtype=torch.bfloat16) * 0.8)(D, H * Dh) * (D ** -0.5)),
            "wo": _w((lambda *s: torch.randn(*s, dtype=torch.bfloat16) * 0.05)(H * Dh, D) * ((H * Dh) ** -0.5)),
        }
    _B_in = _B_setup()

    return {
        "A_x": _A_in["x"],
        "A_k_cache": _A_in["k_cache"],
        "A_v_cache": _A_in["v_cache"],
        "A_wq": _A_in["wq"],
        "A_wo": _A_in["wo"],
        "B_x": _B_in["x"],
        "B_k_cache": _B_in["k_cache"],
        "B_v_cache": _B_in["v_cache"],
        "B_wq": _B_in["wq"],
        "B_wo": _B_in["wo"],
    }

def reference(A_x, A_k_cache, A_v_cache, A_wq, A_wo, B_x, B_k_cache, B_v_cache, B_wq, B_wo):
    def _A_ref(x, k_cache, v_cache, wq, wo):
        B, Sq, D = x.shape
        H, Dh = 16, 256
        q = (lambda x, *d: x.permute(*d))((x @ wq).reshape(B, Sq, H, Dh), 0, 2, 1, 3)
        scores = torch.einsum("bhqd,bhkd->bhqk", q, k_cache) * (Dh ** -0.5)
        p = _softmax(scores, axis=-1)
        o = torch.einsum("bhqk,bhkd->bhqd", p, v_cache)
        return (lambda x, *d: x.permute(*d))(o, 0, 2, 1, 3).reshape(B, Sq, H * Dh) @ wo

    def _B_ref(x, k_cache, v_cache, wq, wo):
        B, Sq, D = x.shape
        H, Dh = 16, 256
        q = (lambda x, *d: x.permute(*d))((x @ wq).reshape(B, Sq, H, Dh), 0, 2, 1, 3)
        scores = torch.einsum("bhqd,bhkd->bhqk", q, k_cache) * (Dh ** -0.5)
        p = _softmax(scores, axis=-1)
        o = torch.einsum("bhqk,bhkd->bhqd", p, v_cache)
        return (lambda x, *d: x.permute(*d))(o, 0, 2, 1, 3).reshape(B, Sq, H * Dh) @ wo

    a = _A_ref(A_x, A_k_cache, A_v_cache, A_wq, A_wo)
    b = _B_ref(B_x, B_k_cache, B_v_cache, B_wq, B_wo)
    return torch.concatenate([a, b], axis=-1)
```

```cpp
#include <cuda_runtime.h>
#include <cuda_bf16.h>
#include <cuda.h>
#include <stdint.h>

namespace {

constexpr int KV_SLOTS = 4;
constexpr int P_SLOTS  = 5;
constexpr int P_SLOTS2 = 7;
constexpr int KV_BYTES = 16384;
constexpr int P_BYTES  = 20480;
constexpr int OT_BYTES = 12288;
constexpr int OFF_KV   = 0;
constexpr int OFF_Q    = OFF_KV + KV_SLOTS * KV_BYTES;
constexpr int OFF_P    = OFF_Q + 4 * OT_BYTES;
constexpr int OFF_ST   = OFF_P + P_SLOTS * P_BYTES;
constexpr int OFF_BAR  = OFF_ST + OT_BYTES;
constexpr int SMEM_BYTES = OFF_BAR + 1024 + 1024;
static_assert(SMEM_BYTES <= 232448, "smem");

constexpr int KV_INFLIGHT = 2;
constexpr int WIDE_UNTIL  = 16;
constexpr int O0_GAP      = 1000;

constexpr int BAR_KVFULL = 0, BAR_KVEMPTY = 4, BAR_WFULL = 8, BAR_WEMPTY = 13, BAR_PKFULL = 18, BAR_OFULL = 23,
              BAR_PAIR = 30, BAR_XFULL = 37, BAR_XEMPTY = 41, BAR_OSL = 44, BAR_SDONE = 52, BAR_Q1 = 54,
              BAR_STFREE = 58, BAR_OGO = 59;
constexpr int OFF_SEQ = 512;

struct Params {
  CUtensorMap tmK[2], tmV[2], tmWq[2], tmWo[2], tmX[2];
  const __nv_bfloat16* wq[2];
  const __nv_bfloat16* x[2];
  const __nv_bfloat16* k[2];
  __nv_bfloat16* out;
  uint32_t zero;
};

__device__ __align__(1024) uint8_t g_O[16 * 16 * 4 * OT_BYTES];
__device__ __align__(128) unsigned g_cnt[16 * 2 * 4 * 8];
__device__ unsigned g_epoch;
__device__ unsigned g_done;

__device__ __forceinline__ uint32_t smem_u32(const void* p) { return (uint32_t)__cvta_generic_to_shared(p); }
__device__ __forceinline__ void mbar_init(uint32_t bar, int cnt) {
  asm volatile("mbarrier.init.shared::cta.b64 [%0], %1;" ::"r"(bar), "r"(cnt) : "memory");
}
__device__ __forceinline__ void mbar_expect_tx(uint32_t bar, uint32_t bytes) {
  asm volatile("mbarrier.arrive.expect_tx.shared::cta.b64 _, [%0], %1;" ::"r"(bar), "r"(bytes) : "memory");
}
__device__ __forceinline__ void mbar_arrive(uint32_t bar) {
  asm volatile("mbarrier.arrive.shared::cta.b64 _, [%0];" ::"r"(bar) : "memory");
}
__device__ __forceinline__ bool mbar_try(uint32_t bar, uint32_t parity) {
  uint32_t ok;
  asm volatile("{\n.reg .pred p;\nmbarrier.try_wait.parity.shared::cta.b64 p, [%1], %2;\nselp.u32 %0, 1, 0, p;\n}\n"
               : "=r"(ok) : "r"(bar), "r"(parity) : "memory");
  return ok != 0;
}
__device__ __forceinline__ bool give_up(uint32_t bar_any, uint32_t t0) {
  const uint32_t fa = (bar_any & ~1023u) + 1016u;
  uint32_t f;
  asm volatile("ld.volatile.shared.u32 %0, [%1];" : "=r"(f) : "r"(fa) : "memory");
  if (f == 0 && (uint32_t)clock() - t0 < (1u << 26)) return false;
  asm volatile("st.volatile.shared.u32 [%0], %1;" ::"r"(fa), "r"(1u) : "memory");
  return true;
}
__device__ __forceinline__ void mbar_wait(uint32_t bar, uint32_t parity) {
  if (mbar_try(bar, parity)) return;
  const uint32_t t0 = (uint32_t)clock();
  uint32_t it = 0;
  while (!mbar_try(bar, parity)) {
    if ((++it & 255u) == 0 && give_up(bar, t0)) break;
  }
}
__device__ __forceinline__ bool elect_one() {
  uint32_t pred;
  asm volatile("{\n.reg .pred p;\nelect.sync _|p, 0xffffffff;\nselp.u32 %0, 1, 0, p;\n}\n" : "=r"(pred));
  return pred != 0;
}
__device__ __forceinline__ void tma_2d(uint32_t dst, const CUtensorMap* tm, int c0, int c1, uint32_t bar) {
  asm volatile("cp.async.bulk.tensor.2d.shared::cluster.global.mbarrier::complete_tx::bytes [%0], [%1, {%3,%4}], [%2];"
               ::"r"(dst), "l"(tm), "r"(bar), "r"(c0), "r"(c1) : "memory");
}
__device__ __forceinline__ void tma_2d_hint(uint32_t dst, const CUtensorMap* tm, int c0, int c1, uint32_t bar, uint64_t pol) {
  asm volatile("cp.async.bulk.tensor.2d.shared::cluster.global.mbarrier::complete_tx::bytes.L2::cache_hint [%0], [%1, {%3,%4}], [%2], %5;"
               ::"r"(dst), "l"(tm), "r"(bar), "r"(c0), "r"(c1), "l"(pol) : "memory");
}
__device__ __forceinline__ void tma_3d(uint32_t dst, const CUtensorMap* tm, int c0, int c1, int c2, uint32_t bar) {
  asm volatile("cp.async.bulk.tensor.3d.shared::cluster.global.mbarrier::complete_tx::bytes [%0], [%1, {%3,%4,%5}], [%2];"
               ::"r"(dst), "l"(tm), "r"(bar), "r"(c0), "r"(c1), "r"(c2) : "memory");
}
__device__ __forceinline__ void tma_2d_mc(uint32_t dst, const CUtensorMap* tm, int c0, int c1, uint32_t bar, uint16_t mask) {
  asm volatile("cp.async.bulk.tensor.2d.shared::cluster.global.mbarrier::complete_tx::bytes.multicast::cluster [%0], [%1, {%3,%4}], [%2], %5;"
               ::"r"(dst), "l"(tm), "r"(bar), "r"(c0), "r"(c1), "h"(mask) : "memory");
}
__device__ __forceinline__ void tma_3d_mc(uint32_t dst, const CUtensorMap* tm, int c0, int c1, int c2, uint32_t bar, uint16_t mask) {
  asm volatile("cp.async.bulk.tensor.3d.shared::cluster.global.mbarrier::complete_tx::bytes.multicast::cluster [%0], [%1, {%3,%4,%5}], [%2], %6;"
               ::"r"(dst), "l"(tm), "r"(bar), "r"(c0), "r"(c1), "r"(c2), "h"(mask) : "memory");
}
__device__ __forceinline__ void bulk_load_mc(uint32_t dst, const void* src, uint32_t bytes, uint32_t bar, uint16_t mask) {
  asm volatile("cp.async.bulk.shared::cluster.global.mbarrier::complete_tx::bytes.multicast::cluster [%0], [%1], %2, [%3], %4;"
               ::"r"(dst), "l"(src), "r"(bytes), "r"(bar), "h"(mask) : "memory");
}
__device__ __forceinline__ uint32_t mapa(uint32_t addr, uint32_t rank) {
  uint32_t r;
  asm("mapa.shared::cluster.u32 %0, %1, %2;" : "=r"(r) : "r"(addr), "r"(rank));
  return r;
}
__device__ __forceinline__ void mbar_arrive_n(uint32_t bar, uint32_t cnt) {
  asm volatile("mbarrier.arrive.shared::cta.b64 _, [%0], %1;" ::"r"(bar), "r"(cnt) : "memory");
}
__device__ __forceinline__ void mbar_arrive_cluster(uint32_t bar, uint32_t cnt) {
  asm volatile("mbarrier.arrive.shared::cluster.b64 _, [%0], %1;" ::"r"(bar), "r"(cnt) : "memory");
}
__device__ __forceinline__ void cluster_arrive() { asm volatile("barrier.cluster.arrive.relaxed.aligned;" ::: "memory"); }
__device__ __forceinline__ void cluster_wait() { asm volatile("barrier.cluster.wait.acquire.aligned;" ::: "memory"); }
__device__ __forceinline__ void sts_volatile(uint32_t a, uint32_t v) {
  asm volatile("st.volatile.shared.u32 [%0], %1;" ::"r"(a), "r"(v) : "memory");
}
__device__ __forceinline__ uint32_t touch256(const void* p) {
  uint32_t v;
  asm volatile("ld.global.L2::256B.u32 %0, [%1];" : "=r"(v) : "l"(p) : "memory");
  return v;
}
__device__ __forceinline__ void prefetch_tmap(const CUtensorMap* tm) {
  asm volatile("prefetch.tensormap [%0];" ::"l"(tm) : "memory");
}
__device__ __forceinline__ void wg_fence() { asm volatile("wgmma.fence.sync.aligned;" ::: "memory"); }
__device__ __forceinline__ void wg_commit() { asm volatile("wgmma.commit_group.sync.aligned;" ::: "memory"); }
template <int N> __device__ __forceinline__ void wg_wait() { asm volatile("wgmma.wait_group.sync.aligned %0;" ::"n"(N) : "memory"); }
template <int N> __device__ __forceinline__ void fence_regs(float (&d)[N]) {
#pragma unroll
  for (int i = 0; i < N; i++) asm volatile("" : "+f"(d[i])::"memory");
}
template <int N> __device__ __forceinline__ void zero_regs(float (&d)[N]) {
#pragma unroll
  for (int i = 0; i < N; i++) d[i] = 0.f;
}
__device__ __forceinline__ void bar_sync(int id, int n) { asm volatile("bar.sync %0, %1;" ::"r"(id), "r"(n) : "memory"); }
__device__ __forceinline__ void fence_async_smem() { asm volatile("fence.proxy.async.shared::cta;" ::: "memory"); }
__device__ __forceinline__ void fence_async_global() { asm volatile("fence.proxy.async.global;" ::: "memory"); }

__device__ __forceinline__ uint64_t make_desc(uint32_t addr) {
  uint64_t d;
  asm("mov.b64 %0, {%1, %2};" : "=l"(d) : "r"((addr >> 4) + 0x10000u), "r"(0x40000040u));
  return d;
}
__device__ __forceinline__ uint32_t pack_bf16(float lo, float hi) {
  uint32_t r;
  asm("cvt.rn.bf16x2.f32 %0, %1, %2;" : "=r"(r) : "f"(hi), "f"(lo));
  return r;
}
__device__ __forceinline__ float ex2(float x) {
  float r;
  asm("ex2.approx.ftz.f32 %0, %1;" : "=f"(r) : "f"(x));
  return r;
}
__device__ __forceinline__ float rcp(float x) {
  float r;
  asm("rcp.approx.ftz.f32 %0, %1;" : "=f"(r) : "f"(x));
  return r;
}
__device__ __forceinline__ void stmatrix_x4_trans(uint32_t addr, uint32_t r0, uint32_t r1, uint32_t r2, uint32_t r3) {
  asm volatile("stmatrix.sync.aligned.m8n8.x4.trans.shared.b16 [%0], {%1,%2,%3,%4};"
               ::"r"(addr), "r"(r0), "r"(r1), "r"(r2), "r"(r3) : "memory");
}

template<int TA, int TB>
__device__ __forceinline__ void wgmma_n96_ss(float (&d)[48], uint64_t da, uint64_t db, int scale_d) {
  asm volatile("{\n.reg .pred p;\nsetp.ne.b32 p, %50, 0;\n"
    "wgmma.mma_async.sync.aligned.m64n96k16.f32.bf16.bf16 {%0, %1, %2, %3, %4, %5, %6, %7, %8, %9, %10, %11, %12, %13, %14, %15, %16, %17, %18, %19, %20, %21, %22, %23, %24, %25, %26, %27, %28, %29, %30, %31, %32, %33, %34, %35, %36, %37, %38, %39, %40, %41, %42, %43, %44, %45, %46, %47}, %48, %49, p, 1, 1, %51, %52;\n}\n"
    : "+f"(d[0]), "+f"(d[1]), "+f"(d[2]), "+f"(d[3]), "+f"(d[4]), "+f"(d[5]), "+f"(d[6]), "+f"(d[7]), "+f"(d[8]), "+f"(d[9]), "+f"(d[10]), "+f"(d[11]), "+f"(d[12]), "+f"(d[13]), "+f"(d[14]), "+f"(d[15]), "+f"(d[16]), "+f"(d[17]), "+f"(d[18]), "+f"(d[19]), "+f"(d[20]), "+f"(d[21]), "+f"(d[22]), "+f"(d[23]), "+f"(d[24]), "+f"(d[25]), "+f"(d[26]), "+f"(d[27]), "+f"(d[28]), "+f"(d[29]), "+f"(d[30]), "+f"(d[31]), "+f"(d[32]), "+f"(d[33]), "+f"(d[34]), "+f"(d[35]), "+f"(d[36]), "+f"(d[37]), "+f"(d[38]), "+f"(d[39]), "+f"(d[40]), "+f"(d[41]), "+f"(d[42]), "+f"(d[43]), "+f"(d[44]), "+f"(d[45]), "+f"(d[46]), "+f"(d[47])
    : "l"(da), "l"(db), "r"(scale_d), "n"(TA), "n"(TB));
}

template<int TA, int TB>
__device__ __forceinline__ void wgmma_n128_ss(float (&d)[64], uint64_t da, uint64_t db, int scale_d) {
  asm volatile("{\n.reg .pred p;\nsetp.ne.b32 p, %66, 0;\n"
    "wgmma.mma_async.sync.aligned.m64n128k16.f32.bf16.bf16 {%0, %1, %2, %3, %4, %5, %6, %7, %8, %9, %10, %11, %12, %13, %14, %15, %16, %17, %18, %19, %20, %21, %22, %23, %24, %25, %26, %27, %28, %29, %30, %31, %32, %33, %34, %35, %36, %37, %38, %39, %40, %41, %42, %43, %44, %45, %46, %47, %48, %49, %50, %51, %52, %53, %54, %55, %56, %57, %58, %59, %60, %61, %62, %63}, %64, %65, p, 1, 1, %67, %68;\n}\n"
    : "+f"(d[0]), "+f"(d[1]), "+f"(d[2]), "+f"(d[3]), "+f"(d[4]), "+f"(d[5]), "+f"(d[6]), "+f"(d[7]), "+f"(d[8]), "+f"(d[9]), "+f"(d[10]), "+f"(d[11]), "+f"(d[12]), "+f"(d[13]), "+f"(d[14]), "+f"(d[15]), "+f"(d[16]), "+f"(d[17]), "+f"(d[18]), "+f"(d[19]), "+f"(d[20]), "+f"(d[21]), "+f"(d[22]), "+f"(d[23]), "+f"(d[24]), "+f"(d[25]), "+f"(d[26]), "+f"(d[27]), "+f"(d[28]), "+f"(d[29]), "+f"(d[30]), "+f"(d[31]), "+f"(d[32]), "+f"(d[33]), "+f"(d[34]), "+f"(d[35]), "+f"(d[36]), "+f"(d[37]), "+f"(d[38]), "+f"(d[39]), "+f"(d[40]), "+f"(d[41]), "+f"(d[42]), "+f"(d[43]), "+f"(d[44]), "+f"(d[45]), "+f"(d[46]), "+f"(d[47]), "+f"(d[48]), "+f"(d[49]), "+f"(d[50]), "+f"(d[51]), "+f"(d[52]), "+f"(d[53]), "+f"(d[54]), "+f"(d[55]), "+f"(d[56]), "+f"(d[57]), "+f"(d[58]), "+f"(d[59]), "+f"(d[60]), "+f"(d[61]), "+f"(d[62]), "+f"(d[63])
    : "l"(da), "l"(db), "r"(scale_d), "n"(TA), "n"(TB));
}

template<int TB>
__device__ __forceinline__ void wgmma_n64_rs(float (&d)[32], uint32_t a0, uint32_t a1, uint32_t a2, uint32_t a3, uint64_t db, int scale_d) {
  asm volatile("{\n.reg .pred p;\nsetp.ne.b32 p, %37, 0;\n"
    "wgmma.mma_async.sync.aligned.m64n64k16.f32.bf16.bf16 {%0, %1, %2, %3, %4, %5, %6, %7, %8, %9, %10, %11, %12, %13, %14, %15, %16, %17, %18, %19, %20, %21, %22, %23, %24, %25, %26, %27, %28, %29, %30, %31}, {%32, %33, %34, %35}, %36, p, 1, 1, %38;\n}\n"
    : "+f"(d[0]), "+f"(d[1]), "+f"(d[2]), "+f"(d[3]), "+f"(d[4]), "+f"(d[5]), "+f"(d[6]), "+f"(d[7]), "+f"(d[8]), "+f"(d[9]), "+f"(d[10]), "+f"(d[11]), "+f"(d[12]), "+f"(d[13]), "+f"(d[14]), "+f"(d[15]), "+f"(d[16]), "+f"(d[17]), "+f"(d[18]), "+f"(d[19]), "+f"(d[20]), "+f"(d[21]), "+f"(d[22]), "+f"(d[23]), "+f"(d[24]), "+f"(d[25]), "+f"(d[26]), "+f"(d[27]), "+f"(d[28]), "+f"(d[29]), "+f"(d[30]), "+f"(d[31])
    : "r"(a0), "r"(a1), "r"(a2), "r"(a3), "l"(db), "r"(scale_d), "n"(TB));
}


__device__ __forceinline__ void store_transposed(const float (&acc)[48], uint32_t base, int wq, int lane) {
  const int i = lane & 7, half = (lane >> 3) & 1, jo = lane >> 4;
  const uint32_t chunk = (uint32_t)((2 * wq + half) ^ i) << 4;
#pragma unroll
  for (int jn = 0; jn < 12; jn += 2) {
    const uint32_t row = 8 * (jn + jo) + i;
    stmatrix_x4_trans(base + row * 128 + chunk,
                      pack_bf16(acc[4 * jn + 0], acc[4 * jn + 1]), pack_bf16(acc[4 * jn + 2], acc[4 * jn + 3]),
                      pack_bf16(acc[4 * jn + 4], acc[4 * jn + 5]), pack_bf16(acc[4 * jn + 6], acc[4 * jn + 7]));
  }
}

__device__ __forceinline__ void store_o_slice(const float (&acc)[32], uint32_t rowaddr, int lane, float inva, float invb) {
#pragma unroll
  for (int jn = 0; jn < 8; jn += 2) {
    const uint32_t chunk = (uint32_t)((jn + (lane >> 4)) ^ (lane & 7)) << 4;
    asm volatile("stmatrix.sync.aligned.m8n8.x4.shared.b16 [%0], {%1,%2,%3,%4};" ::"r"(rowaddr + chunk),
                 "r"(pack_bf16(acc[4 * jn] * inva, acc[4 * jn + 1] * inva)),
                 "r"(pack_bf16(acc[4 * jn + 2] * invb, acc[4 * jn + 3] * invb)),
                 "r"(pack_bf16(acc[4 * jn + 4] * inva, acc[4 * jn + 5] * inva)),
                 "r"(pack_bf16(acc[4 * jn + 6] * invb, acc[4 * jn + 7] * invb)) : "memory");
  }
  fence_async_smem();
}

__device__ __forceinline__ uint32_t pslot_addr(uint32_t sb, int slot) {
  return sb + (slot < P_SLOTS ? OFF_P + slot * P_BYTES : OFF_Q + (slot - P_SLOTS) * P_BYTES);
}
__device__ __forceinline__ int pslot_next(int slot, bool wide) {
  if (slot == 4) return 0;
  if (slot == 1 && wide) return 5;
  if (slot == 6) return 2;
  return slot + 1;
}

__global__ void __cluster_dims__(2, 1, 1) __launch_bounds__(512, 1) fused_mha_kernel(const __grid_constant__ Params p) {
  extern __shared__ uint8_t smem_raw[];
  const uint32_t sb = (smem_u32(smem_raw) + 1023u) & ~1023u;
  const uint32_t bars = sb + OFF_BAR;
  const int tid = threadIdx.x, lane = tid & 31;
  const int warp = __shfl_sync(0xffffffffu, tid >> 5, 0), wg = warp >> 2;
  const int cta = blockIdx.x, g = cta >> 3, j = cta & 7, blk = g >> 3, b = g & 7;
  const bool has_o = (j < 7);
  if (warp == 12 || warp == 13) {
    if (tid == 384) {
      sts_volatile(bars + 1016u, 0u);
#pragma unroll
      for (int i = 0; i < 4; i++) {
        mbar_init(bars + 8 * (BAR_KVFULL + i), 1);
        mbar_init(bars + 8 * (BAR_KVEMPTY + i), 2);
      }
      asm volatile("fence.mbarrier_init.release.cluster;" ::: "memory");
    } else if (tid == 416) {
      sts_volatile(bars + 1016u, 0u);
#pragma unroll
      for (int i = 0; i < 4; i++) mbar_init(bars + 8 * (BAR_XFULL + i), 1);
#pragma unroll
      for (int i = 0; i < 5; i++) {
        mbar_init(bars + 8 * (BAR_WFULL + i), 1);
        mbar_init(bars + 8 * (BAR_WEMPTY + i), 1);
        mbar_init(bars + 8 * (BAR_PKFULL + i), 1);
      }
#pragma unroll
      for (int i = 0; i < 3; i++) mbar_init(bars + 8 * (BAR_XEMPTY + i), 2);
      asm volatile("fence.mbarrier_init.release.cluster;" ::: "memory");
    }
    __syncwarp();
    asm volatile("bar.arrive 0, 512;" ::: "memory");
    if (tid == 384) {
#pragma unroll
      for (int kc = 0; kc < KV_SLOTS; kc++) {
        const uint32_t fb = bars + 8 * (BAR_KVFULL + kc);
        mbar_expect_tx(fb, KV_BYTES);
        tma_3d(sb + OFF_KV + kc * KV_BYTES, &p.tmWq[blk], 0, kc * 64, j * 4, fb);
        tma_3d(sb + OFF_KV + kc * KV_BYTES + 8192, &p.tmWq[blk], 0, kc * 64, j * 4 + 1, fb);
      }
    } else if (tid == 416) {
#pragma unroll
      for (int n = 0; n < P_SLOTS; n++) {
        if (n < 4) {
          mbar_expect_tx(bars + 8 * (BAR_XFULL + n), OT_BYTES);
          tma_2d(sb + OFF_Q + n * OT_BYTES, &p.tmX[blk], n * 64, b * 96, bars + 8 * (BAR_XFULL + n));
        }
        const uint32_t fb = bars + 8 * (BAR_WFULL + n);
        mbar_expect_tx(fb, 16384);
        tma_3d(sb + OFF_P + n * P_BYTES, &p.tmWq[blk], 0, n * 64, j * 4 + 2, fb);
        tma_3d(sb + OFF_P + n * P_BYTES + 8192, &p.tmWq[blk], 0, n * 64, j * 4 + 3, fb);
      }
    }
    __syncwarp();
  } else {
    if (tid == 32) {
#pragma unroll
      for (int i = 0; i < 7; i++) {
        mbar_init(bars + 8 * (BAR_OFULL + i), 1);
        mbar_init(bars + 8 * (BAR_PAIR + i), 4);
        mbar_expect_tx(bars + 8 * (BAR_OFULL + i), P_BYTES);
      }
      asm volatile("fence.mbarrier_init.release.cluster;" ::: "memory");
    } else if (tid == 0) {
#pragma unroll
      for (int i = 0; i < 8; i++) mbar_init(bars + 8 * (BAR_OSL + i), 6);
#pragma unroll
      for (int i = 0; i < 4; i++) mbar_init(bars + 8 * (BAR_Q1 + i), 1);
      mbar_init(bars + 8 * BAR_SDONE, 2);
      mbar_init(bars + 8 * BAR_STFREE, 1);
      mbar_init(bars + 8 * BAR_OGO, 1);
      asm volatile("fence.mbarrier_init.release.cluster;" ::: "memory");
    } else if (tid == 64) {
      prefetch_tmap(&p.tmK[blk]); prefetch_tmap(&p.tmV[blk]); prefetch_tmap(&p.tmWo[blk]);
    } else if (warp == 3) {
      sts_volatile(bars + OFF_SEQ + 4 * lane, 0u);
      sts_volatile(bars + OFF_SEQ + 128 + 4 * lane, 0u);
    }
    bar_sync(0, 512);
  }
  cluster_arrive();
  const bool leader = (j & 1) == 0;
  const uint32_t pairb = mapa(bars + 8 * BAR_PAIR, leader ? 1 : 0);
  auto pair_release = [&](int sl, uint32_t cnt) {
    mbar_arrive_n(bars + 8 * (BAR_PAIR + sl), cnt);
    mbar_arrive_cluster(pairb + 8 * sl, cnt);
  };
  const int krow0 = (b * 16 + j) << 9;

  if (wg == 3) {
    asm volatile("setmaxnreg.dec.sync.aligned.u32 32;");
    uint64_t pol;
    asm volatile("createpolicy.fractional.L2::evict_first.b64 %0, 1.0;" : "=l"(pol));
    if (warp == 12) {
      int slot = 0, ph = 1;
#pragma unroll 1
      for (int kc = KV_SLOTS; kc < 7; kc++) {
        const uint32_t fb = bars + 8 * (BAR_KVFULL + slot);
        const uint32_t dst = sb + OFF_KV + slot * KV_BYTES;
        mbar_wait(bars + 8 * (BAR_KVEMPTY + slot), ph ^ 1);
        if (elect_one()) {
          mbar_expect_tx(fb, KV_BYTES);
          tma_3d(dst, &p.tmWq[blk], 0, kc * 64, j * 4, fb);
          tma_3d(dst + 8192, &p.tmWq[blk], 0, kc * 64, j * 4 + 1, fb);
        }
        if (++slot == KV_SLOTS) { slot = 0; ph ^= 1; }
      }
      int tslot = slot, tph = ph, landed = 0;
#pragma unroll 1
      for (int n = 0; n < 59; n++) {
        const int i = n < 4 ? 2 * n + 1 : n + 5;
        const int w = i >> 5, isv = (i >> 4) & 1, r = i & 15;
        const int kc = isv ? (r & 3) : (r >> 2);
        const int dc = isv ? (r >> 2) : (r & 3);
        const uint32_t fb = bars + 8 * (BAR_KVFULL + slot);
        const uint32_t dst = sb + OFF_KV + slot * KV_BYTES;
        const int row = krow0 + w * 4096 + kc * 128;
        const CUtensorMap* tm = isv ? &p.tmV[blk] : &p.tmK[blk];
        const int win = (i < WIDE_UNTIL) ? KV_SLOTS : KV_INFLIGHT;
        mbar_wait(bars + 8 * (BAR_KVEMPTY + slot), ph ^ 1);
        if (elect_one()) mbar_expect_tx(fb, KV_BYTES);
        while (landed <= n - win) {
          mbar_wait(bars + 8 * (BAR_KVFULL + tslot), tph);
          if (++tslot == KV_SLOTS) { tslot = 0; tph ^= 1; }
          landed++;
        }
        if (elect_one()) tma_2d_hint(dst, tm, dc * 64, row, fb, pol);
        if (++slot == KV_SLOTS) { slot = 0; ph ^= 1; }
      }
    } else if (warp == 13) {
      unsigned epoch = 0;
      {
        int slot = 0, ph = 1;
#pragma unroll 1
        for (int n = P_SLOTS; n < 12; n++) {
          const uint32_t dst = sb + OFF_P + slot * P_BYTES;
          if (n < 8) {
            const int xs = n - P_SLOTS;
            mbar_wait(bars + 8 * (BAR_XEMPTY + xs), 0);
            if (elect_one()) {
              const uint32_t fb = bars + 8 * (BAR_XFULL + xs);
              mbar_expect_tx(fb, OT_BYTES);
              tma_2d(sb + OFF_Q + xs * OT_BYTES, &p.tmX[blk], (4 + xs) * 64, b * 96, fb);
            }
          }
          mbar_wait(bars + 8 * (BAR_WEMPTY + slot), ph ^ 1);
          if (n < 7) {
            if (elect_one()) {
              const uint32_t fb = bars + 8 * (BAR_WFULL + slot);
              mbar_expect_tx(fb, 16384);
              tma_3d(dst, &p.tmWq[blk], 0, n * 64, j * 4 + 2, fb);
              tma_3d(dst + 8192, &p.tmWq[blk], 0, n * 64, j * 4 + 3, fb);
            }
          } else {
            const int i = 2 * (n - 7);
            if (elect_one()) {
              const uint32_t fb = bars + 8 * (BAR_PKFULL + slot);
              mbar_expect_tx(fb, KV_BYTES);
              tma_2d_hint(dst, &p.tmK[blk], (i & 3) * 64, krow0 + (i >> 2) * 128, fb, pol);
            }
          }
          if (++slot == P_SLOTS) { slot = 0; ph ^= 1; }
        }
      }
      if (lane == 0) {
        asm volatile("ld.acquire.gpu.global.u32 %0, [%1];" : "=r"(epoch) : "l"(&g_epoch) : "memory");
        const unsigned d = atomicAdd(&g_done, 1u);
        if (d == gridDim.x - 1) {
          g_done = 0;
          __threadfence();
          atomicExch(&g_epoch, epoch + 1);
        }
      }
      __syncwarp();
      cluster_wait();
      {
        int slot = 2, cnt = 0, ph = 0;
#pragma unroll 1
        for (int t = 0; t < 4; t++) {
#pragma unroll 1
          for (int kc = 0; kc < 7; kc++) {
            const uint32_t dst = sb + OFF_P + slot * P_BYTES;
            const uint32_t fb = bars + 8 * (BAR_OFULL + slot);
            mbar_wait(bars + 8 * (BAR_PAIR + slot), ph);
            if (elect_one()) {
              if (leader) {
                tma_2d_mc(dst, &p.tmX[blk], kc * 64, b * 96, fb, 3);
              } else {
                tma_3d_mc(dst + OT_BYTES, &p.tmWq[blk], 0, kc * 64, (7 + j) * 4 + t, fb, 1);
                tma_3d(dst + OT_BYTES, &p.tmWq[blk], 0, kc * 64, (8 + j) * 4 + t, fb);
              }
            }
            if (++slot == P_SLOTS) slot = 0;
            if (++cnt == P_SLOTS) { cnt = 0; ph ^= 1; }
          }
        }
        __syncwarp();
        if (lane == 0) mbar_arrive(bars + 8 * BAR_OGO);
      }
      if (leader) {
        const unsigned expected = __shfl_sync(0xffffffffu, epoch, 0) + 1u;
        const uint32_t t0 = (uint32_t)clock();
        const uint32_t rseq = mapa(bars + OFF_SEQ, 1);
        const uint32_t lt = (1u << lane) - 1u;
#pragma unroll 1
        for (int ow = 0; ow < 2; ow++) {
          const unsigned* flag = &g_cnt[g * 64 + ow * 32 + lane];
          uint32_t seen = 0;
          while (seen != 0xffffffffu) {
            unsigned v;
            asm volatile("ld.acquire.gpu.global.u32 %0, [%1];" : "=r"(v) : "l"(flag) : "memory");
            uint32_t ready = __ballot_sync(0xffffffffu, (int)(v - expected) >= 0);
            if (ready == seen) {
              if (!give_up(bars, t0)) { __nanosleep(20); continue; }
              ready = 0xffffffffu;
            }
            const uint32_t fresh = ready & ~seen;
            if ((fresh >> lane) & 1) {
              const uint32_t pos = 4u * (ow * 32 + __popc(seen) + __popc(fresh & lt));
              const uint32_t hs1 = (ow * 8 + (lane & 7)) * 4 + (lane >> 3) + 1;
              asm volatile("st.volatile.shared::cluster.u32 [%0], %1;" ::"r"(rseq + pos), "r"(hs1) : "memory");
              fence_async_global();
              asm volatile("st.release.cta.shared.u32 [%0], %1;" ::"r"(bars + OFF_SEQ + pos), "r"(hs1) : "memory");
            }
            seen = ready;
            __syncwarp();
          }
        }
      }
    } else if (warp == 14) {
      cluster_wait();
      mbar_wait(bars + 8 * BAR_OGO, 0);
      const bool both = (j < 6);
      int slot = (28 + 2) % P_SLOTS;
      uint32_t pph = 0x03u;
      const uint32_t t0 = (uint32_t)clock();
      const uint8_t* obase = g_O + (size_t)(g * 64) * OT_BYTES;
      uint32_t tissue = t0 - 100000;
#pragma unroll 1
      for (int m = 0; m < 64; m++) {
        const uint32_t dst = pslot_addr(sb, slot);
        const uint32_t fb = bars + 8 * (BAR_OFULL + slot);
        mbar_wait(bars + 8 * (BAR_PAIR + slot), (pph >> slot) & 1);
        pph ^= 1u << slot;
        uint32_t hs1, it = 0;
        while (true) {
          asm volatile("ld.acquire.cta.shared.u32 %0, [%1];" : "=r"(hs1) : "r"(bars + OFF_SEQ + 4u * m) : "memory");
          hs1 = __shfl_sync(0xffffffffu, hs1, 0);
          if (hs1) break;
          __nanosleep(30);
          if ((++it & 255u) == 0 && give_up(bars, t0)) { hs1 = 1; break; }
        }
        const int hs = hs1 - 1;
        if (m < 32) {
          while (__shfl_sync(0xffffffffu, (uint32_t)clock(), 0) - tissue < O0_GAP) __nanosleep(50);
          tissue = __shfl_sync(0xffffffffu, (uint32_t)clock(), 0);
        }
        if (elect_one()) {
          if (leader) {
            bulk_load_mc(dst, obase + (size_t)hs * OT_BYTES, OT_BYTES, fb, both ? 3 : 1);
          } else {
            tma_2d_mc(dst + OT_BYTES, &p.tmWo[blk], j * 64 - 64, hs * 64, fb, 1);
            if (both) tma_2d(dst + OT_BYTES, &p.tmWo[blk], j * 64, hs * 64, fb);
          }
        }
        slot = pslot_next(slot, m >= 32);
      }
      cluster_arrive();
      cluster_wait();
    } else if (warp == 15 && lane == 0) {
#pragma unroll 1
      for (int ws = 0; ws < 8; ws++) {
        uint8_t* dst = g_O + (size_t)((g * 16 + (ws >> 2) * 8 + j) * 4 + (ws & 3)) * OT_BYTES;
        mbar_wait(bars + 8 * (BAR_OSL + ws), 0);
        asm volatile("cp.async.bulk.global.shared::cta.bulk_group [%0], [%1], %2;" ::"l"(dst), "r"(sb + OFF_ST), "r"(OT_BYTES) : "memory");
        asm volatile("cp.async.bulk.commit_group;" ::: "memory");
        asm volatile("cp.async.bulk.wait_group.read 0;" ::: "memory");
        mbar_arrive(bars + 8 * BAR_STFREE);
        asm volatile("cp.async.bulk.wait_group 0;" ::: "memory");
        asm volatile("red.release.gpu.global.add.u32 [%0], 1;" ::"l"(&g_cnt[(g * 8 + ws) * 8 + j]) : "memory");
      }
    }
  } else if (wg == 2) {
    asm volatile("setmaxnreg.dec.sync.aligned.u32 80;");
    const int wq = warp & 3;
    const bool elect = (tid == 256);
    uint32_t ophase = 0;
    int slot = 2;
    const int npass = has_o ? 5 : 4;
    int nrel = 0;
    {
      const int t = tid - 256, c64 = cta & 63;
      uint32_t v0 = 0;
      if (t < 48) v0 = touch256((const char*)p.wq[blk] + (size_t)(64 * (4 + (t >> 4)) + c64) * 8192 + (t & 15) * 256);
      else if (t < 90) v0 = touch256((const char*)p.x[blk] + (size_t)b * 86016 + j * 10752 + (t - 48) * 256);
      {
        const uint32_t t0 = (uint32_t)clock();
        while (!mbar_try(bars + 8 * BAR_WFULL, 0) && (uint32_t)clock() - t0 < 8192u) {}
      }
      const char* kp = (const char*)p.k[blk] + (size_t)krow0 * 512 + t * 256;
      const uint32_t v1 = touch256(kp), v2 = touch256(kp + 32768);
      if ((v0 | v1 | v2) & p.zero) sts_volatile(bars + 1008u, 1u);
    }
    cluster_wait();
    auto release = [&](int sl) {
      if (elect) {
        mbar_expect_tx(bars + 8 * (BAR_OFULL + sl), P_BYTES);
        if (nrel + P_SLOTS2 < 92) pair_release(sl, (j == 6 && nrel >= 28) ? 4 : 2);
      }
      nrel++;
    };
#pragma unroll 1
    for (int pass = 0; pass < npass; pass++) {
      float acc[48];
      zero_regs(acc);
      const int ntile = pass < 4 ? 7 : 64;
      int pend = -1;
#pragma unroll 1
      for (int t = 0; t < ntile; t++) {
        const uint32_t fb = bars + 8 * (BAR_OFULL + slot);
        const uint32_t par = (ophase >> slot) & 1;
        mbar_wait(fb, par);
        ophase ^= 1u << slot;
        const uint32_t base = pslot_addr(sb, slot);
        wg_fence();
#pragma unroll
        for (int ks = 0; ks < 4; ks++)
          wgmma_n96_ss<1, 0>(acc, make_desc(base + OT_BYTES + ks * 2048), make_desc(base + ks * 32), 1);
        wg_commit();
        if (pend >= 0) {
          wg_wait<1>();
          release(pend);
        }
        pend = slot;
        slot = pslot_next(slot, pass == 4 && t >= 32);
      }
      wg_wait<0>();
      release(pend);
      fence_regs(acc);
      if (pass < 4) {
        if (pass == 0) mbar_wait(bars + 8 * (BAR_SDONE + 0), 0);
        store_transposed(acc, sb + OFF_Q + pass * OT_BYTES, wq, lane);
        fence_async_smem();
        bar_sync(2, 128);
        if (elect) mbar_arrive(bars + 8 * (BAR_Q1 + pass));
      } else {
        const uint32_t st = sb + OFF_KV + wq * 3072;
        const int i = lane & 7, half = (lane >> 3) & 1, jo = lane >> 4;
#pragma unroll
        for (int jn = 0; jn < 12; jn += 2) {
          const uint32_t row = 8 * (jn + jo) + i;
          stmatrix_x4_trans(st + row * 32 + ((half ^ ((i >> 2) & 1)) << 4),
                            pack_bf16(acc[4 * jn + 0], acc[4 * jn + 1]), pack_bf16(acc[4 * jn + 2], acc[4 * jn + 3]),
                            pack_bf16(acc[4 * jn + 4], acc[4 * jn + 5]), pack_bf16(acc[4 * jn + 6], acc[4 * jn + 7]));
        }
        __syncwarp();
        __nv_bfloat16* outp = p.out + (size_t)(b * 96 + (lane >> 1)) * 896 + blk * 448 + j * 64 + wq * 16 + (lane & 1) * 8;
        const uint32_t rd = st + (lane >> 1) * 32 + (((lane & 1) ^ ((lane >> 3) & 1)) << 4);
#pragma unroll
        for (int it = 0; it < 6; it++) {
          uint4 v;
          asm volatile("ld.shared.v4.u32 {%0,%1,%2,%3}, [%4];" : "=r"(v.x), "=r"(v.y), "=r"(v.z), "=r"(v.w) : "r"(rd + it * 512));
          asm volatile("st.global.v4.u32 [%0], {%1,%2,%3,%4};" ::"l"(outp + (size_t)it * 16 * 896), "r"(v.x), "r"(v.y),
                       "r"(v.z), "r"(v.w) : "memory");
        }
      }
    }
  } else {
    asm volatile("setmaxnreg.inc.sync.aligned.u32 200;");
    const int wq = warp & 3;
    const bool elect = (tid & 127) == 96;
    int kslot = 0, kph = 0;
    {
      float acc0[48], acc1[48];
      zero_regs(acc0);
      zero_regs(acc1);
      const int nslots = wg == 0 ? KV_SLOTS : P_SLOTS;
      const uint32_t fullb = bars + 8 * (wg == 0 ? BAR_KVFULL : BAR_WFULL);
      const uint32_t emptyb = bars + 8 * (wg == 0 ? BAR_KVEMPTY : BAR_WEMPTY);
      const uint32_t rbase = sb + (wg == 0 ? OFF_KV : OFF_P);
      const uint32_t rstride = wg == 0 ? KV_BYTES : P_BYTES;
      int slot = 0, ph = 0;
#pragma unroll 1
      for (int kc = 0; kc < 7; kc++) {
        const int xs = kc & 3;
        mbar_wait(bars + 8 * (BAR_XFULL + xs), kc >> 2);
        mbar_wait(fullb + 8 * slot, ph);
        const uint32_t wb = rbase + slot * rstride;
        const uint32_t xb = sb + OFF_Q + xs * OT_BYTES;
        wg_fence();
#pragma unroll
        for (int ks = 0; ks < 4; ks++) {
          wgmma_n96_ss<1, 0>(acc0, make_desc(wb + ks * 2048), make_desc(xb + ks * 32), 1);
          wgmma_n96_ss<1, 0>(acc1, make_desc(wb + 8192 + ks * 2048), make_desc(xb + ks * 32), 1);
        }
        wg_commit();
        wg_wait<0>();
        if (elect) {
          mbar_arrive(emptyb + 8 * slot);
          if (wg == 0) mbar_arrive(emptyb + 8 * slot);
          if (kc < 3) mbar_arrive(bars + 8 * (BAR_XEMPTY + kc));
        }
        if (++slot == nslots) { slot = 0; ph ^= 1; }
        if (++kslot == KV_SLOTS) { kslot = 0; kph ^= 1; }
      }
      cluster_wait();
      fence_regs(acc0);
      fence_regs(acc1);
      bar_sync(1, 256);
      store_transposed(acc0, sb + OFF_Q + (2 * wg) * OT_BYTES, wq, lane);
      store_transposed(acc1, sb + OFF_Q + (2 * wg + 1) * OT_BYTES, wq, lane);
      fence_async_smem();
      bar_sync(1, 256);
    }
#pragma unroll 1
    for (int w = 0; w < 2; w++) {
      uint32_t pk[128];
      float ma = -INFINITY, mb = -INFINITY, la = 0.f, lb = 0.f;
      float fa[3], fb3[3];
      const float c = 1.4426950408889634f / 16.0f;
      const uint32_t qb = sb + OFF_Q + wg * 6144;
#pragma unroll
      for (int kc = 0; kc < 4; kc++) {
        float acc[64];
        zero_regs(acc);
#pragma unroll
        for (int dc = 0; dc < 4; dc++) {
          if (kc == 0 && w == 1) mbar_wait(bars + 8 * (BAR_Q1 + dc), 0);
          constexpr int kParked[16] = {2, -1, 3, -1, 4, -1, 0, -1, 1, -1, -1, -1, -1, -1, -1, -1};
          const int ps = kParked[kc * 4 + dc];
          const bool parked = ps >= 0 && w == 0;
          mbar_wait(parked ? bars + 8 * (BAR_PKFULL + ps) : bars + 8 * (BAR_KVFULL + kslot), parked ? 0 : kph);
          const uint32_t kb = parked ? sb + OFF_P + ps * P_BYTES : sb + OFF_KV + kslot * KV_BYTES;
          wg_fence();
#pragma unroll
          for (int ks = 0; ks < 4; ks++)
            wgmma_n128_ss<0, 0>(acc, make_desc(qb + dc * OT_BYTES + ks * 32), make_desc(kb + ks * 32), 1);
          wg_commit();
          wg_wait<0>();
          if (elect) {
            if (parked) pair_release(ps, 1);
            else mbar_arrive(bars + 8 * (BAR_KVEMPTY + kslot));
            if (kc == 3 && dc == 3) {
              if (w == 0) {
                mbar_arrive(bars + 8 * BAR_SDONE);
              } else {
                pair_release(5, 1);
                pair_release(6, 1);
              }
            }
          }
          if (!parked && ++kslot == KV_SLOTS) { kslot = 0; kph ^= 1; }
        }
        fence_regs(acc);
        {
#pragma unroll
          for (int jj = 0; jj < 32; jj++) {
            const uint32_t r2 = pack_bf16(acc[2 * jj], acc[2 * jj + 1]);
            acc[2 * jj] = __uint_as_float(r2 << 16);
            acc[2 * jj + 1] = __uint_as_float(r2 & 0xFFFF0000u);
          }
          float xa0 = ma, xa1 = acc[1], xb0 = mb, xb1 = acc[3];
          xa0 = fmaxf(xa0, acc[0]);
          xb0 = fmaxf(xb0, acc[2]);
#pragma unroll
          for (int jj = 1; jj < 16; jj++) {
            xa0 = fmaxf(xa0, acc[4 * jj]);     xa1 = fmaxf(xa1, acc[4 * jj + 1]);
            xb0 = fmaxf(xb0, acc[4 * jj + 2]); xb1 = fmaxf(xb1, acc[4 * jj + 3]);
          }
          float xa = fmaxf(xa0, xa1), xb = fmaxf(xb0, xb1);
          xa = fmaxf(xa, __shfl_xor_sync(0xffffffffu, xa, 1));
          xb = fmaxf(xb, __shfl_xor_sync(0xffffffffu, xb, 1));
          xa = fmaxf(xa, __shfl_xor_sync(0xffffffffu, xa, 2));
          xb = fmaxf(xb, __shfl_xor_sync(0xffffffffu, xb, 2));
          const float na = -xa * c, nb = -xb * c;
          if (kc > 0) {
            fa[kc - 1] = ex2(fmaf(ma, c, na));
            fb3[kc - 1] = ex2(fmaf(mb, c, nb));
            la *= fa[kc - 1];
            lb *= fb3[kc - 1];
          }
          ma = xa; mb = xb;
#pragma unroll
          for (int jj = 0; jj < 16; jj++) {
            const float e0 = ex2(fmaf(acc[4 * jj], c, na));
            const float e1 = ex2(fmaf(acc[4 * jj + 1], c, na));
            const float f0 = ex2(fmaf(acc[4 * jj + 2], c, nb));
            const float f1 = ex2(fmaf(acc[4 * jj + 3], c, nb));
            la += e0 + e1;
            lb += f0 + f1;
            pk[32 * kc + 2 * jj] = pack_bf16(e0, e1);
            pk[32 * kc + 2 * jj + 1] = pack_bf16(f0, f1);
          }
        }
      }
      la += __shfl_xor_sync(0xffffffffu, la, 1);
      lb += __shfl_xor_sync(0xffffffffu, lb, 1);
      la += __shfl_xor_sync(0xffffffffu, la, 2);
      lb += __shfl_xor_sync(0xffffffffu, lb, 2);
      const float inva = rcp(la), invb = rcp(lb);
      const uint32_t orow = sb + OFF_ST + (48 * wg + 16 * wq + (lane & 15)) * 128;
#pragma unroll 1
      for (int s = 0; s < 4; s++) {
        float acc[32];
        zero_regs(acc);
#pragma unroll
        for (int kc = 0; kc < 4; kc++) {
          mbar_wait(bars + 8 * (BAR_KVFULL + kslot), kph);
          const uint32_t vb = sb + OFF_KV + kslot * KV_BYTES;
          wg_fence();
#pragma unroll
          for (int ks = 0; ks < 8; ks++)
            wgmma_n64_rs<1>(acc, pk[32 * kc + 4 * ks], pk[32 * kc + 4 * ks + 1], pk[32 * kc + 4 * ks + 2],
                            pk[32 * kc + 4 * ks + 3], make_desc(vb + ks * 2048), 1);
          wg_commit();
          wg_wait<0>();
          if (elect) mbar_arrive(bars + 8 * (BAR_KVEMPTY + kslot));
          if (++kslot == KV_SLOTS) { kslot = 0; kph ^= 1; }
          fence_regs(acc);
          if (kc < 3) {
#pragma unroll
            for (int jj = 0; jj < 8; jj++) {
              acc[4 * jj] *= fa[kc];      acc[4 * jj + 1] *= fa[kc];
              acc[4 * jj + 2] *= fb3[kc]; acc[4 * jj + 3] *= fb3[kc];
            }
          }
        }
        if (wq < 3) {
          mbar_wait(bars + 8 * BAR_STFREE, (s & 1) ^ 1);
          store_o_slice(acc, orow, lane, inva, invb);
          __syncwarp();
          if (lane == 0) mbar_arrive(bars + 8 * (BAR_OSL + w * 4 + s));
        }
      }
    }
  }
}

typedef CUresult (*EncodeFn)(CUtensorMap*, CUtensorMapDataType, cuuint32_t, void*, const cuuint64_t*, const cuuint64_t*,
                             const cuuint32_t*, const cuuint32_t*, CUtensorMapInterleave, CUtensorMapSwizzle,
                             CUtensorMapL2promotion, CUtensorMapFloatOOBfill);

bool encode(EncodeFn fn, CUtensorMap* tm, const void* ptr, int rank, const cuuint64_t* dims, const cuuint64_t* strides,
            const cuuint32_t* box, CUtensorMapL2promotion promo) {
  cuuint32_t es[5] = {1, 1, 1, 1, 1};
  return fn(tm, CU_TENSOR_MAP_DATA_TYPE_BFLOAT16, (cuuint32_t)rank, const_cast<void*>(ptr), dims, strides, box, es,
            CU_TENSOR_MAP_INTERLEAVE_NONE, CU_TENSOR_MAP_SWIZZLE_128B, promo, CU_TENSOR_MAP_FLOAT_OOB_FILL_NONE) == CUDA_SUCCESS;
}

}

extern "C" void kernel_launch(void* const* d_in, const int* in_sizes, int n_in, void* d_out, int out_size) {
  (void)in_sizes; (void)n_in; (void)out_size;
  static EncodeFn enc = nullptr;
  if (!enc) {
    cudaDriverEntryPointQueryResult qr;
    void* fn = nullptr;
    cudaGetDriverEntryPoint("cuTensorMapEncodeTiled", &fn, cudaEnableDefault, &qr);
    enc = (EncodeFn)fn;
    cudaFuncSetAttribute(fused_mha_kernel, cudaFuncAttributeMaxDynamicSharedMemorySize, SMEM_BYTES);
  }
  Params p;
  bool ok = enc != nullptr;
  for (int blk = 0; blk < 2 && ok; blk++) {
    const void* x = d_in[5 * blk + 0];
    const void* k = d_in[5 * blk + 1];
    const void* v = d_in[5 * blk + 2];
    const void* wq = d_in[5 * blk + 3];
    const void* wo = d_in[5 * blk + 4];
    {
      cuuint64_t dims[2] = {256, 65536}; cuuint64_t st[1] = {512}; cuuint32_t box[2] = {64, 128};
      ok = ok && encode(enc, &p.tmK[blk], k, 2, dims, st, box, CU_TENSOR_MAP_L2_PROMOTION_L2_128B);
      ok = ok && encode(enc, &p.tmV[blk], v, 2, dims, st, box, CU_TENSOR_MAP_L2_PROMOTION_L2_128B);
    }
    {
      cuuint64_t dims[3] = {64, 448, 64}; cuuint64_t st[2] = {8192, 128}; cuuint32_t box[3] = {64, 64, 1};
      ok = ok && encode(enc, &p.tmWq[blk], wq, 3, dims, st, box, CU_TENSOR_MAP_L2_PROMOTION_L2_128B);
    }
    {
      cuuint64_t dims[2] = {448, 4096}; cuuint64_t st[1] = {896}; cuuint32_t box[2] = {64, 64};
      ok = ok && encode(enc, &p.tmWo[blk], wo, 2, dims, st, box, CU_TENSOR_MAP_L2_PROMOTION_L2_128B);
    }
    {
      cuuint64_t dims[2] = {448, 768}; cuuint64_t st[1] = {896}; cuuint32_t box[2] = {64, 96};
      ok = ok && encode(enc, &p.tmX[blk], x, 2, dims, st, box, CU_TENSOR_MAP_L2_PROMOTION_L2_128B);
    }
  }
  for (int blk = 0; blk < 2; blk++) { p.x[blk] = (const __nv_bfloat16*)d_in[5 * blk]; p.wq[blk] = (const __nv_bfloat16*)d_in[5 * blk + 3]; p.k[blk] = (const __nv_bfloat16*)d_in[5 * blk + 1]; }
  p.out = (__nv_bfloat16*)d_out;
  p.zero = 0;
  if (!ok) return;
  fused_mha_kernel<<<128, 512, SMEM_BYTES>>>(p);
}
```
